```python
import torch

def _softmax(x, axis=-1):
    return torch.softmax(x, dim=axis)

def _gelu(x):
    return torch.nn.functional.gelu(x, approximate='tanh')

def _silu(x):
    return torch.nn.functional.silu(x)

def _sigmoid(x):
    return torch.sigmoid(x)

def _layernorm(x, axis=-1, eps=1e-05):
    m = x.mean(dim=axis, keepdim=True)
    v = x.var(dim=axis, keepdim=True, unbiased=False)
    return (x - m) / torch.sqrt(v + eps)

def _scatter_add(tgt, idx, src, axis=0):
    return tgt.clone().index_add_(axis, idx, src)

def _segment_sum(src, seg, n):
    out = torch.zeros((n,) + src.shape[1:], dtype=src.dtype)
    return out.index_add_(0, seg, src)

def _pad(x, pw):
    flat = tuple((v for pair in reversed(pw) for v in pair))
    return torch.nn.functional.pad(x, flat)
kernel_name = 'adaLN_cond__sliding_block__dense_activation_relu__prompt'

def setup_inputs():

    _w = lambda a: (lambda t: t.to(torch.bfloat16) if t.is_floating_point() else t)(torch.as_tensor(a))

    def _A_setup():
        B, S, D = (1, 2048, 512)
        return {'x': _w((lambda *s: torch.randn(*s, dtype=torch.bfloat16) * 0.05)(B, S, D)), 'wqkv': _w((lambda *s: torch.randn(*s, dtype=torch.bfloat16) * 0.05)(D, 3 * D)), 'wo': _w((lambda *s: torch.randn(*s, dtype=torch.bfloat16) * 0.05)(D, D))}
    _A_in = _A_setup()

    def _B_setup():
        B, S, D, Dff = (1, 2048, 512, 1792)
        return {'x': _w((lambda *s: torch.randn(*s, dtype=torch.bfloat16) * 0.05)(B, S, D)), 'w1': _w((lambda *s: torch.randn(*s, dtype=torch.bfloat16) * 0.05)(D, Dff)), 'w2': _w((lambda *s: torch.randn(*s, dtype=torch.bfloat16) * 0.05)(Dff, D))}
    _B_in = _B_setup()
    return {'A_x': _A_in['x'], 'A_wqkv': _A_in['wqkv'], 'A_wo': _A_in['wo'], 'B_x': _B_in['x'], 'B_w1': _B_in['w1'], 'B_w2': _B_in['w2'], 'c': _w((lambda *s: torch.randn(*s, dtype=torch.bfloat16) * 0.1)(1, 512) * 8.0), 'w_mod': _w((lambda *s: torch.randn(*s, dtype=torch.bfloat16) * 0.1)(512, 6 * 512) * 512 ** (-0.5) * 8.0)}

def reference(A_x, A_wqkv, A_wo, B_x, B_w1, B_w2, c, w_mod):

    def _A_ref(x, wqkv, wo):
        B, S, D = x.shape
        H = 32
        Dh = D // H
        W = 256
        qkv = (lambda x, *d: x.permute(*d))((x @ wqkv).reshape(B, S, 3, H, Dh), 2, 0, 3, 1, 4)
        q, k, v = (qkv[0], qkv[1], qkv[2])
        scores = torch.einsum('bhqd,bhkd->bhqk', q, k) * Dh ** (-0.5)
        idx = torch.arange(S)
        mask = (idx[:, None] - idx[None, :] >= 0) & (idx[:, None] - idx[None, :] < W)
        scores = torch.where(mask[None, None], scores, -1000000000.0)
        p = _softmax(scores, axis=-1)
        o = torch.einsum('bhqk,bhkd->bhqd', p, v)
        return (lambda x, *d: x.permute(*d))(o, 0, 2, 1, 3).reshape(B, S, D) @ wo

    def _B_ref(x, w1, w2):
        h = torch.einsum('bsd,df->bsf', x, w1)
        zero = torch.zeros_like(h)
        h = torch.maximum(h, zero)
        return torch.einsum('bsf,fd->bsd', h, w2)
    x = A_x
    mod = (_silu(c) @ w_mod).reshape(c.shape[0], 6, 1, -1)
    sa, ca, ga, sb, cb, gb = (mod[:, 0].clone(), mod[:, 1].clone(), mod[:, 2].clone(), mod[:, 3].clone(), mod[:, 4].clone(), mod[:, 5].clone())
    h = _layernorm(x, axis=-1) * (1 + ca) + sa
    x = x + ga * _A_ref(h, A_wqkv, A_wo)
    h = _layernorm(x, axis=-1) * (1 + cb) + sb
    x = x + gb * _B_ref(h, B_w1, B_w2)
    return x
```

```cpp
#include <cuda_runtime.h>
#include <cuda_bf16.h>
#include <cuda.h>
#include <stdint.h>
#include <type_traits>

#define DEVI __device__ __forceinline__
constexpr int NPOS = 14, CH = 16384;
constexpr int TAB_OFF = NPOS * CH, GAB_OFF = TAB_OFF + 2048, RED_OFF = GAB_OFF + 256, BAR_OFF = RED_OFF + 392, SMEM_BYTES = BAR_OFF + 320;
enum { B_FULL = 0, B_EMPTY = 14, B_X = 28, B_XFREE = 32, B_TABFREE, B_OLD, B_MOD2, B_N };
constexpr uint32_t SPIN_MAX = 1u << 17;

__device__ uint32_t g_epoch;
__device__ __align__(16) uint32_t g_part[4][1024];
__device__ __align__(16) uint32_t g_mod[3072];
__device__ uint4 g_kv[128][8][256], g_o[128][4][256], g_x1[128][4][256], g_h[128][14][256], g_p[128][4][256], g_stats[128][64];
#define STAMP(i)
#define STAMPX(i)
#define CNT(i)

DEVI void mbar_init(uint32_t b, int c) { asm volatile("mbarrier.init.shared::cta.b64 [%0], %1;" ::"r"(b), "r"(c)); }
DEVI void mbar_expect(uint32_t b, int bytes) { asm volatile("mbarrier.arrive.expect_tx.shared::cta.b64 _, [%0], %1;" ::"r"(b), "r"(bytes) : "memory"); }
DEVI void mbar_arrive(uint32_t b) { asm volatile("mbarrier.arrive.shared::cta.b64 _, [%0];" ::"r"(b) : "memory"); }
DEVI void mbar_wait(uint32_t b, int par) {
  uint32_t ok, it = 0;
  do {
    asm volatile("{\n.reg .pred p;\nmbarrier.try_wait.parity.shared::cta.b64 p, [%1], %2;\nselp.u32 %0, 1, 0, p;\n}" : "=r"(ok) : "r"(b), "r"(par) : "memory");
    if (++it > SPIN_MAX) break;
  } while (!ok);
}
DEVI void warp_arrive(uint32_t b) { __syncwarp(); if ((threadIdx.x & 31) == 0) mbar_arrive(b); }
DEVI void fence_async() { asm volatile("fence.proxy.async.shared::cta;" ::: "memory"); }
DEVI void tma3(uint32_t dst, const CUtensorMap* tm, uint32_t bar, int c0, int c1, int c2) {
  asm volatile("cp.async.bulk.tensor.3d.shared::cluster.global.mbarrier::complete_tx::bytes [%0], [%1, {%3, %4, %5}], [%2];" ::"r"(dst), "l"(tm), "r"(bar), "r"(c0), "r"(c1), "r"(c2) : "memory");
}
DEVI uint4 ld_rlx4(const void* p) { uint4 v; asm volatile("ld.relaxed.gpu.global.v4.u32 {%0,%1,%2,%3}, [%4];" : "=r"(v.x), "=r"(v.y), "=r"(v.z), "=r"(v.w) : "l"(p) : "memory"); return v; }
DEVI uint2 ld_rlx2(const void* p) { uint2 v; asm volatile("ld.relaxed.gpu.global.v2.u32 {%0,%1}, [%2];" : "=r"(v.x), "=r"(v.y) : "l"(p) : "memory"); return v; }
DEVI void st_rlx8(void* p, uint32_t a, uint32_t b) { asm volatile("st.relaxed.gpu.global.b32 [%0], %1;" ::"l"(p), "r"(a | (b & 0xffff)) : "memory"); }
DEVI bool stale(uint4 v, uint32_t ep) { return (((v.x ^ ep) | (v.y ^ ep) | (v.z ^ ep) | (v.w ^ ep)) & 0xffff) != 0; }
DEVI uint4 ldg_nc4(const void* p) { uint4 v; asm volatile("ld.global.nc.L1::no_allocate.v4.u32 {%0,%1,%2,%3}, [%4];" : "=r"(v.x), "=r"(v.y), "=r"(v.z), "=r"(v.w) : "l"(p)); return v; }
DEVI void ldsm4(uint32_t (&r)[4], uint32_t a) { asm volatile("ldmatrix.sync.aligned.m8n8.x4.shared.b16 {%0,%1,%2,%3}, [%4];" : "=r"(r[0]), "=r"(r[1]), "=r"(r[2]), "=r"(r[3]) : "r"(a)); }
DEVI void ldsm4t(uint32_t (&r)[4], uint32_t a) { asm volatile("ldmatrix.sync.aligned.m8n8.x4.trans.shared.b16 {%0,%1,%2,%3}, [%4];" : "=r"(r[0]), "=r"(r[1]), "=r"(r[2]), "=r"(r[3]) : "r"(a)); }
DEVI void stsm4(uint32_t a, uint32_t r0, uint32_t r1, uint32_t r2, uint32_t r3) { asm volatile("stmatrix.sync.aligned.m8n8.x4.shared.b16 [%0], {%1,%2,%3,%4};" ::"r"(a), "r"(r0), "r"(r1), "r"(r2), "r"(r3) : "memory"); }
DEVI uint4 lds4(uint32_t a) { uint4 v; asm volatile("ld.shared.v4.u32 {%0,%1,%2,%3}, [%4];" : "=r"(v.x), "=r"(v.y), "=r"(v.z), "=r"(v.w) : "r"(a)); return v; }
DEVI uint32_t lds1(uint32_t a) { uint32_t v; asm volatile("ld.shared.u32 %0, [%1];" : "=r"(v) : "r"(a)); return v; }
DEVI void sts1(uint32_t a, uint32_t v) { asm volatile("st.shared.u32 [%0], %1;" ::"r"(a), "r"(v) : "memory"); }
DEVI uint32_t pack(float lo, float hi) { uint32_t r; asm("cvt.rn.bf16x2.f32 %0, %1, %2;" : "=r"(r) : "f"(hi), "f"(lo)); return r; }
DEVI uint32_t pack_relu(float lo, float hi) { uint32_t r; asm("cvt.rn.relu.bf16x2.f32 %0, %1, %2;" : "=r"(r) : "f"(hi), "f"(lo)); return r; }
DEVI float blo(uint32_t v) { return __uint_as_float(v << 16); }
DEVI float bhi(uint32_t v) { return __uint_as_float(v & 0xffff0000u); }
DEVI float bfr(float v) { return __bfloat162float(__float2bfloat16_rn(v)); }
DEVI uint32_t hfma2(uint32_t a, uint32_t b, uint32_t c) { uint32_t r; asm("fma.rn.bf16x2 %0, %1, %2, %3;" : "=r"(r) : "r"(a), "r"(b), "r"(c)); return r; }
DEVI float ex2(float x) { float r; asm("ex2.approx.ftz.f32 %0, %1;" : "=f"(r) : "f"(x)); return r; }
DEVI void mma(float* d, uint32_t a0, uint32_t a1, uint32_t a2, uint32_t a3, uint32_t b0, uint32_t b1, float c0, float c1, float c2, float c3) {
  asm("mma.sync.aligned.m16n8k16.row.col.f32.bf16.bf16.f32 {%0,%1,%2,%3}, {%4,%5,%6,%7}, {%8,%9}, {%10,%11,%12,%13};"
      : "=f"(d[0]), "=f"(d[1]), "=f"(d[2]), "=f"(d[3]) : "r"(a0), "r"(a1), "r"(a2), "r"(a3), "r"(b0), "r"(b1), "f"(c0), "f"(c1), "f"(c2), "f"(c3));
}
DEVI void mma_acc(float* d, uint32_t a0, uint32_t a1, uint32_t a2, uint32_t a3, uint32_t b0, uint32_t b1) { mma(d, a0, a1, a2, a3, b0, b1, d[0], d[1], d[2], d[3]); }
DEVI void mma8(float* d, uint32_t a) {
  asm("mma.sync.aligned.m16n8k8.row.col.f32.bf16.bf16.f32 {%0,%1,%2,%3}, {%4,%5}, {%4}, {%0,%1,%2,%3};" : "+f"(d[0]), "+f"(d[1]), "+f"(d[2]), "+f"(d[3]) : "r"(a), "r"(0x3f803f80u));
}
DEVI void wg_fence() { asm volatile("wgmma.fence.sync.aligned;" ::: "memory"); }
DEVI void wg_commit() { asm volatile("wgmma.commit_group.sync.aligned;" ::: "memory"); }
template <int N> DEVI void wg_wait() { asm volatile("wgmma.wait_group.sync.aligned %0;" ::"n"(N) : "memory"); }
DEVI void bar_cons() { asm volatile("bar.sync 1, 256;" ::: "memory"); }
DEVI uint64_t mkdesc(uint32_t addr, uint32_t lbo, uint32_t sbo, uint32_t sw) {
  return (uint64_t)((addr & 0x3FFFF) >> 4) | ((uint64_t)(lbo >> 4) << 16) | ((uint64_t)(sbo >> 4) << 32) | ((uint64_t)sw << 62);
}
template <int N> DEVI void keep(float (&d)[N]) {
#pragma unroll
  for (int i = 0; i < N; i++) asm volatile("" : "+f"(d[i])::"memory");
}
__device__ __forceinline__ void wgmma_rs_n64(float (&d)[32], const uint32_t (&a)[4], uint64_t db, int sd) {
  asm volatile("{\n.reg .pred p;\nsetp.ne.b32 p, %37, 0;\n"
    "wgmma.mma_async.sync.aligned.m64n64k16.f32.bf16.bf16 {%0, %1, %2, %3, %4, %5, %6, %7, %8, %9, %10, %11, %12, %13, %14, %15, %16, %17, %18, %19, %20, %21, %22, %23, %24, %25, %26, %27, %28, %29, %30, %31}, {%32,%33,%34,%35}, %36, p, 1, 1, 1;\n}\n"
    : "+f"(d[0]), "+f"(d[1]), "+f"(d[2]), "+f"(d[3]), "+f"(d[4]), "+f"(d[5]), "+f"(d[6]), "+f"(d[7]), "+f"(d[8]), "+f"(d[9]), "+f"(d[10]), "+f"(d[11]), "+f"(d[12]), "+f"(d[13]), "+f"(d[14]), "+f"(d[15]), "+f"(d[16]), "+f"(d[17]), "+f"(d[18]), "+f"(d[19]), "+f"(d[20]), "+f"(d[21]), "+f"(d[22]), "+f"(d[23]), "+f"(d[24]), "+f"(d[25]), "+f"(d[26]), "+f"(d[27]), "+f"(d[28]), "+f"(d[29]), "+f"(d[30]), "+f"(d[31])
    : "r"(a[0]), "r"(a[1]), "r"(a[2]), "r"(a[3]), "l"(db), "r"(sd));
}
__device__ __forceinline__ void wgmma_rs_n128(float (&d)[64], const uint32_t (&a)[4], uint64_t db, int sd) {
  asm volatile("{\n.reg .pred p;\nsetp.ne.b32 p, %69, 0;\n"
    "wgmma.mma_async.sync.aligned.m64n128k16.f32.bf16.bf16 {%0, %1, %2, %3, %4, %5, %6, %7, %8, %9, %10, %11, %12, %13, %14, %15, %16, %17, %18, %19, %20, %21, %22, %23, %24, %25, %26, %27, %28, %29, %30, %31, %32, %33, %34, %35, %36, %37, %38, %39, %40, %41, %42, %43, %44, %45, %46, %47, %48, %49, %50, %51, %52, %53, %54, %55, %56, %57, %58, %59, %60, %61, %62, %63}, {%64,%65,%66,%67}, %68, p, 1, 1, 1;\n}\n"
    : "+f"(d[0]), "+f"(d[1]), "+f"(d[2]), "+f"(d[3]), "+f"(d[4]), "+f"(d[5]), "+f"(d[6]), "+f"(d[7]), "+f"(d[8]), "+f"(d[9]), "+f"(d[10]), "+f"(d[11]), "+f"(d[12]), "+f"(d[13]), "+f"(d[14]), "+f"(d[15]), "+f"(d[16]), "+f"(d[17]), "+f"(d[18]), "+f"(d[19]), "+f"(d[20]), "+f"(d[21]), "+f"(d[22]), "+f"(d[23]), "+f"(d[24]), "+f"(d[25]), "+f"(d[26]), "+f"(d[27]), "+f"(d[28]), "+f"(d[29]), "+f"(d[30]), "+f"(d[31]), "+f"(d[32]), "+f"(d[33]), "+f"(d[34]), "+f"(d[35]), "+f"(d[36]), "+f"(d[37]), "+f"(d[38]), "+f"(d[39]), "+f"(d[40]), "+f"(d[41]), "+f"(d[42]), "+f"(d[43]), "+f"(d[44]), "+f"(d[45]), "+f"(d[46]), "+f"(d[47]), "+f"(d[48]), "+f"(d[49]), "+f"(d[50]), "+f"(d[51]), "+f"(d[52]), "+f"(d[53]), "+f"(d[54]), "+f"(d[55]), "+f"(d[56]), "+f"(d[57]), "+f"(d[58]), "+f"(d[59]), "+f"(d[60]), "+f"(d[61]), "+f"(d[62]), "+f"(d[63])
    : "r"(a[0]), "r"(a[1]), "r"(a[2]), "r"(a[3]), "l"(db), "r"(sd));
}
__device__ __forceinline__ void wgmma_rs_n224(float (&d)[112], const uint32_t (&a)[4], uint64_t db, int sd) {
  asm volatile("{\n.reg .pred p;\nsetp.ne.b32 p, %117, 0;\n"
    "wgmma.mma_async.sync.aligned.m64n224k16.f32.bf16.bf16 {%0, %1, %2, %3, %4, %5, %6, %7, %8, %9, %10, %11, %12, %13, %14, %15, %16, %17, %18, %19, %20, %21, %22, %23, %24, %25, %26, %27, %28, %29, %30, %31, %32, %33, %34, %35, %36, %37, %38, %39, %40, %41, %42, %43, %44, %45, %46, %47, %48, %49, %50, %51, %52, %53, %54, %55, %56, %57, %58, %59, %60, %61, %62, %63, %64, %65, %66, %67, %68, %69, %70, %71, %72, %73, %74, %75, %76, %77, %78, %79, %80, %81, %82, %83, %84, %85, %86, %87, %88, %89, %90, %91, %92, %93, %94, %95, %96, %97, %98, %99, %100, %101, %102, %103, %104, %105, %106, %107, %108, %109, %110, %111}, {%112,%113,%114,%115}, %116, p, 1, 1, 1;\n}\n"
    : "+f"(d[0]), "+f"(d[1]), "+f"(d[2]), "+f"(d[3]), "+f"(d[4]), "+f"(d[5]), "+f"(d[6]), "+f"(d[7]), "+f"(d[8]), "+f"(d[9]), "+f"(d[10]), "+f"(d[11]), "+f"(d[12]), "+f"(d[13]), "+f"(d[14]), "+f"(d[15]), "+f"(d[16]), "+f"(d[17]), "+f"(d[18]), "+f"(d[19]), "+f"(d[20]), "+f"(d[21]), "+f"(d[22]), "+f"(d[23]), "+f"(d[24]), "+f"(d[25]), "+f"(d[26]), "+f"(d[27]), "+f"(d[28]), "+f"(d[29]), "+f"(d[30]), "+f"(d[31]), "+f"(d[32]), "+f"(d[33]), "+f"(d[34]), "+f"(d[35]), "+f"(d[36]), "+f"(d[37]), "+f"(d[38]), "+f"(d[39]), "+f"(d[40]), "+f"(d[41]), "+f"(d[42]), "+f"(d[43]), "+f"(d[44]), "+f"(d[45]), "+f"(d[46]), "+f"(d[47]), "+f"(d[48]), "+f"(d[49]), "+f"(d[50]), "+f"(d[51]), "+f"(d[52]), "+f"(d[53]), "+f"(d[54]), "+f"(d[55]), "+f"(d[56]), "+f"(d[57]), "+f"(d[58]), "+f"(d[59]), "+f"(d[60]), "+f"(d[61]), "+f"(d[62]), "+f"(d[63]), "+f"(d[64]), "+f"(d[65]), "+f"(d[66]), "+f"(d[67]), "+f"(d[68]), "+f"(d[69]), "+f"(d[70]), "+f"(d[71]), "+f"(d[72]), "+f"(d[73]), "+f"(d[74]), "+f"(d[75]), "+f"(d[76]), "+f"(d[77]), "+f"(d[78]), "+f"(d[79]), "+f"(d[80]), "+f"(d[81]), "+f"(d[82]), "+f"(d[83]), "+f"(d[84]), "+f"(d[85]), "+f"(d[86]), "+f"(d[87]), "+f"(d[88]), "+f"(d[89]), "+f"(d[90]), "+f"(d[91]), "+f"(d[92]), "+f"(d[93]), "+f"(d[94]), "+f"(d[95]), "+f"(d[96]), "+f"(d[97]), "+f"(d[98]), "+f"(d[99]), "+f"(d[100]), "+f"(d[101]), "+f"(d[102]), "+f"(d[103]), "+f"(d[104]), "+f"(d[105]), "+f"(d[106]), "+f"(d[107]), "+f"(d[108]), "+f"(d[109]), "+f"(d[110]), "+f"(d[111])
    : "r"(a[0]), "r"(a[1]), "r"(a[2]), "r"(a[3]), "l"(db), "r"(sd));
}

DEVI void st_ll(uint4* p, uint32_t a, uint32_t b, uint32_t c, uint32_t d, uint32_t tg) {
  asm volatile("st.relaxed.gpu.global.v4.u32 [%0], {%1,%2,%3,%4};" ::"l"(p), "r"((a & ~1u) | tg), "r"(b), "r"(c), "r"(d) : "memory");
}
DEVI void ld_ll(uint32_t (&v)[4], const uint4* p) { asm volatile("ld.relaxed.gpu.global.v4.u32 {%0,%1,%2,%3}, [%4];" : "=r"(v[0]), "=r"(v[1]), "=r"(v[2]), "=r"(v[3]) : "l"(p) : "memory"); }
template <int N, class F> DEVI void ld_grp(uint32_t (*v)[4], F src) {
#pragma unroll
  for (int i = 0; i < N; i++) ld_ll(v[i], src(i));
}
template <int N, class F> DEVI void fix_grp(uint32_t (*v)[4], F src, uint32_t tg, int ci) {
  for (uint32_t it = 0; it < SPIN_MAX; it++) {
    uint32_t bad = 0;
#pragma unroll
    for (int i = 0; i < N; i++) bad |= v[i][0] ^ tg;
    if (!__any_sync(~0u, bad & 1)) break;
    ld_grp<N>(v, src);
    CNT(ci);
  }
}
DEVI constexpr int perm(int i) { return i; }
DEVI int colblk(int g) { return (g & 3) * 2 + (g >> 2); }
DEVI float silu_bf(float c) { return bfr(__fdividef(c, 1.f + __expf(-c))); }
DEVI void put_tab(uint32_t tab, int k, bool isc, uint4 v) {
  const float o = isc ? 1.f : 0.f;
  const uint32_t a = tab + (k >> 4) * 64 + ((k >> 1) & 3) * 16 + ((k >> 3) & 1) * 4 + (isc ? 0 : 8);
  sts1(a, pack(bhi(v.x) + o, bhi(v.y) + o)); sts1(a + 16, pack(bhi(v.z) + o, bhi(v.w) + o));
}
DEVI uint32_t dup(float v) { return pack(v, v); }
#define RST 15
#define PF 0
#define PACE 0
#define EARLY 0
#define UN1X 1
#define UN2X 3
constexpr int UN1 = UN1X, UN2 = UN2X;
#define GK 24
#define K16 0
#define SX 2
#define KB 4
#define KL 0
#define RH 4
#define RS1 0
#define THR 2
#define OLDE 1
#define STG 1500
#define LDJ 0
#define WOJ 0
#define BBF(K) asm volatile("{\n.reg .pred p;\nsetp.eq.u32 p, %0, %1;\n@p exit;\n}" ::"r"(bid), "n"(0x1000000 + (K)))

struct Params { const __nv_bfloat16 *x, *wqkv, *wo, *w1, *w2, *c, *wmod; const uint32_t* epoch; };

__global__ void __launch_bounds__(384, 1)
fused_kernel(const __grid_constant__ CUtensorMap tm_x, const __grid_constant__ CUtensorMap tm_q,
             const __grid_constant__ CUtensorMap tm_wo, const __grid_constant__ CUtensorMap tm_w1, const __grid_constant__ CUtensorMap tm_w2,
             const __grid_constant__ CUtensorMap tm_out, const Params P) {
  extern __shared__ __align__(1024) uint8_t smem[];
  const uint32_t sb = (uint32_t)__cvta_generic_to_shared(smem);
  const int tid = threadIdx.x, warp = __shfl_sync(~0u, tid >> 5, 0), lane = tid & 31;
  const int bid = blockIdx.x, m = bid >> 3, g = bid & 7;
  auto BAR = [&](int i) { return sb + BAR_OFF + i * 8; };
  uint4 wm0, wm1;
  float c0v, c1v;
  if (warp < 8) {
    const int row = (bid >> 5) * 128 + (tid >> 2);
    wm0 = ldg_nc4(P.wmod + (size_t)row * 3072 + (bid & 31) * 32 + (tid & 3) * 8);
    wm1 = ldg_nc4(P.wmod + (size_t)(row + 64) * 3072 + (bid & 31) * 32 + (tid & 3) * 8);
    c0v = __bfloat162float(P.c[row]);
    c1v = __bfloat162float(P.c[row + 64]);
  }
  if (warp == 10) sts1(sb + RED_OFF + 388, (uint32_t)(size_t)g_part);
  if (tid == 352 && (PF & 1)) asm volatile("cp.async.bulk.prefetch.L2.global [%0], 16384;" ::"l"(P.x + bid * 8192) : "memory");
  if (tid == 352 && (PF & 2)) asm volatile("cp.async.bulk.prefetch.L2.global [%0], 12288;" ::"l"(P.wqkv + bid * 6144) : "memory");
  if (warp == 9) {
    uint32_t e;
    asm volatile("ld.relaxed.gpu.global.u32 %0, [%1];" : "=r"(e) : "l"(P.epoch) : "memory");
    sts1(sb + RED_OFF + 384, e + 1);
    asm volatile("bar.arrive 3, 384;" ::: "memory");
  }
  if (tid == 256) {
    for (int i = 0; i < 4; i++) mbar_init(BAR(B_X + i), 1);
    fence_async();
    for (int i = 0; i < 4; i++) { mbar_expect(BAR(B_X + i), 2 * CH); tma3(sb + (i < 3 ? 4 + 2 * i : 12) * CH, &tm_x, BAR(B_X + i), 0, m * 128, 2 * i); }
    asm volatile("prefetch.tensormap [%0];" ::"l"(&tm_q) : "memory");
    for (int i = 0; i < NPOS; i++) { mbar_init(BAR(B_FULL + i), 1); mbar_init(BAR(B_EMPTY + i), 8); }
    mbar_init(BAR(B_XFREE), 8); mbar_init(BAR(B_TABFREE), 8); mbar_init(BAR(B_OLD), 8); mbar_init(BAR(B_MOD2), 2);
    fence_async();
  }
  if (warp == 8) { __syncwarp(); asm volatile("bar.arrive 3, 384;" ::: "memory"); }

  if (warp >= 8) {
    asm volatile("setmaxnreg.dec.sync.aligned.u32 40;");
    if (warp == 8) {
      if (lane == 0) {
        const int cb = colblk(g);
        uint32_t pend[THR];
        for (int i = 0; i < THR; i++) pend[i] = BAR(B_X + 4 - THR + i);
        auto go = [&](int pos, int bytes, int par) {
          mbar_wait(pend[0] & ~1u, pend[0] & 1);
          for (int i = 0; i + 1 < THR; i++) pend[i] = pend[i + 1];
          pend[THR - 1] = BAR(B_FULL + pos) | par;
          mbar_expect(BAR(B_FULL + pos), bytes);
          return sb + pos * CH;
        };
        for (int i = 0; i < 8; i++) {
          const int pos = i < 4 ? i : i + 6;
          if (i == 5) mbar_wait(BAR(B_XFREE), 0);
          tma3(go(pos, CH, 0), &tm_q, BAR(B_FULL + pos), g * 64, (i & 3) * 128, 1 + (i >> 2));
        }
        for (int i = 0; i < 4; i++) { mbar_wait(BAR(B_EMPTY + i), 0); tma3(go(i, CH, 1), &tm_q, BAR(B_FULL + i), g * 64, i * 128, 0); }
        for (int i = 0; i < 4; i++) { mbar_wait(BAR(B_EMPTY + 10 + i), 0); tma3(go(10 + i, CH, 1), &tm_wo, BAR(B_FULL + 10 + i), cb * 64, i * 16, 0); }
        for (int t = 0; t < 30; t++) {
          const int rd = t >= 28 ? 2 : (t >= 14 ? 1 : 0), pos = perm(t - rd * 14);
          if (rd == 0 && pos >= 4 && pos < 10) { if (pos == 4) mbar_wait(BAR(B_OLD), 0); }
          else mbar_wait(BAR(B_EMPTY + pos), (rd & 1) ^ 1);
          if (t < 16) tma3(go(pos, 14336, rd & 1), &tm_w1, BAR(B_FULL + pos), 0, colblk((g + (t >> 1)) & 7) * 64 + (t & 1) * 32, g * 7);
          else {
            const uint32_t dst = go(pos, CH, rd & 1);
            for (int e = 0; e < 2; e++) {
              const int u = (t - 16) * 2 + e, v = u - 7;
              const int row = u < 7 ? g * 224 + u * 32 : ((g & 4) | ((g + 1 + v % 3) & 3)) * 224 + ((v / 3 + 4) % 7) * 32;
              tma3(dst + e * 8192, &tm_w2, BAR(B_FULL + pos), 0, row, (g & 3) * 2);
            }
          }
        }
      }
    } else if (warp >= 10) {
      asm volatile("bar.sync 3, 384;" ::: "memory");
      const uint32_t ep = lds1(sb + RED_OFF + 384);
      mbar_wait(BAR(B_XFREE), 0);
      const int t = tid - 320;
      if (t < 3) {
        const char* p = t == 0 ? (const char*)P.wo + bid * 4096 : (t == 1 ? (const char*)P.w1 : (const char*)P.w2) + bid * 14336;
        asm volatile("cp.async.bulk.prefetch.L2.global [%0], %1;" ::"l"(p), "r"(t == 0 ? 4096 : 14336) : "memory");
      }
      float acc[8];
#pragma unroll
      for (int j = 0; j < 8; j++) acc[j] = 0.f;
#pragma unroll 4
      for (int i = 0; i < 16; i++) {
        const int r = (t >> 1) + 32 * i;
        const uint4 w = ldg_nc4(P.wmod + (size_t)r * 3072 + 1024 + bid * 16 + (t & 1) * 8);
        const float s = silu_bf(__bfloat162float(P.c[r]));
        acc[0] += s * blo(w.x); acc[1] += s * bhi(w.x); acc[2] += s * blo(w.y); acc[3] += s * bhi(w.y);
        acc[4] += s * blo(w.z); acc[5] += s * bhi(w.z); acc[6] += s * blo(w.w); acc[7] += s * bhi(w.w);
      }
#pragma unroll
      for (int j = 0; j < 8; j++)
#pragma unroll
        for (int o = 2; o < 32; o <<= 1) acc[j] += __shfl_xor_sync(~0u, acc[j], o);
      float* red = (float*)(smem + RED_OFF + 256);
      if (lane < 2) {
#pragma unroll
        for (int j = 0; j < 8; j++) red[(warp - 10) * 16 + lane * 8 + j] = acc[j];
      }
      asm volatile("bar.sync 2, 64;" ::: "memory");
      if (t < 16) st_rlx8(&g_mod[1024 + bid * 16 + t], __float_as_uint(bfr(red[t] + red[16 + t])), ep);
      mbar_wait(BAR(B_TABFREE), 0);
      __nanosleep(1000);
      uint4 v[5];
      const uint32_t* gp = &g_mod[(t & 16 ? 2560 : 1024) + colblk(g) * 64 + (t & 15) * 4];
      for (uint32_t it = 0; it < SPIN_MAX; it++) {
        bool bad = false;
#pragma unroll
        for (int i = 0; i < 5; i++) v[i] = ld_rlx4(i < 4 ? &g_mod[1536 + i * 256 + t * 4] : gp);
#pragma unroll
        for (int i = 0; i < 5; i++) bad |= stale(v[i], ep);
        if (!bad) break;
        __nanosleep(300);
      }
#pragma unroll
      for (int i = 0; i < 4; i++) put_tab(sb + TAB_OFF, (i & 1) * 256 + t * 4, i >> 1, v[i]);
      if (t < 32) { sts1(sb + GAB_OFF + t * 8, pack(bhi(v[4].x), bhi(v[4].y))); sts1(sb + GAB_OFF + t * 8 + 4, pack(bhi(v[4].z), bhi(v[4].w))); }
      warp_arrive(BAR(B_MOD2));
    }
  } else {
    const int q = lane & 3, r = lane >> 2;
    auto release = [&](int pos) { if (lane == 0) mbar_arrive(BAR(B_EMPTY + pos)); };
    uint32_t ep;
    {
      const float s0 = silu_bf(c0v), s1 = silu_bf(c1v);
      float v[8] = {s0 * blo(wm0.x) + s1 * blo(wm1.x), s0 * bhi(wm0.x) + s1 * bhi(wm1.x), s0 * blo(wm0.y) + s1 * blo(wm1.y), s0 * bhi(wm0.y) + s1 * bhi(wm1.y),
                    s0 * blo(wm0.z) + s1 * blo(wm1.z), s0 * bhi(wm0.z) + s1 * bhi(wm1.z), s0 * blo(wm0.w) + s1 * blo(wm1.w), s0 * bhi(wm0.w) + s1 * bhi(wm1.w)};
#pragma unroll
      for (int j = 0; j < 4; j++) { const bool u = lane & 4; const float sn = u ? v[j] : v[j + 4], kp = u ? v[j + 4] : v[j]; v[j] = kp + __shfl_xor_sync(~0u, sn, 4); }
#pragma unroll
      for (int j = 0; j < 2; j++) { const bool u = lane & 8; const float sn = u ? v[j] : v[j + 2], kp = u ? v[j + 2] : v[j]; v[j] = kp + __shfl_xor_sync(~0u, sn, 8); }
      { const bool u = lane & 16; const float sn = u ? v[0] : v[1], kp = u ? v[1] : v[0]; v[0] = kp + __shfl_xor_sync(~0u, sn, 16); }
      float* red = (float*)(smem + 11 * CH);
      red[warp * 32 + (lane & 3) * 8 + (lane & 4) + ((lane >> 3) & 1) * 2 + (lane >> 4)] = v[0];
      asm volatile("bar.sync 3, 384;" ::: "memory");
      ep = lds1(sb + RED_OFF + 384);
      if (tid < 32) {
        float s = 0.f;
#pragma unroll
        for (int w = 0; w < 8; w++) s += red[w * 32 + tid];
        st_rlx8(&g_part[bid >> 5][(bid & 31) * 32 + tid], __float_as_uint(s) & ~0xffu, ep & 0xff);
      }
    }
    STAMP(0);
    STAMP(1);
    asm volatile("setmaxnreg.inc.sync.aligned.u32 232;");
    const uint32_t tg = ep & 1;
    auto reset = [&](uint4* p, int n) { for (int i = 0; i < n; i++) st_ll(p + i * 256, 0, 0, 0, 0, tg ^ 1); };
    if (RST & 1) reset(&g_kv[bid][4][tid], 4);
    const uint32_t srow = sb + (warp * 16 + (lane & 15)) * 128;
    const uint32_t ssw = ((lane >> 4) ^ (lane & 7)) << 4;
    const uint32_t tabq = sb + TAB_OFF + q * 16;
    uint32_t qf[16];
    {
      uint32_t a[32][4], u0, u1, l0, l1, n0, n1;
      {
        uint32_t v[4][4];
        auto msrc = [&](int i) { return (const uint4*)&g_part[i][tid * 4]; };
        float g0[8] = {}, g1[8] = {};
#pragma unroll
        for (int k = 0; k < 32; k++) {
          if (k % 8 == 0) mbar_wait(BAR(B_X + k / 8), 0);
          if (k == GK) ld_grp<4>(v, msrc);
          if (k == 8) STAMP(22);
          if (k == 0) STAMP(23);
          ldsm4(a[k], srow + (k < 24 ? 4 + k / 4 : 6 + k / 4) * CH + (ssw ^ ((k & 3) * 32)));
          if (K16) {
            mma_acc(g0 + (k & 1) * 4, a[k][0], 0x3f803f80u, a[k][2], 0x3f803f80u, a[k][0], a[k][2]);
            mma_acc(g1 + (k & 1) * 4, a[k][1], 0x3f803f80u, a[k][3], 0x3f803f80u, a[k][1], a[k][3]);
            continue;
          }
          mma8(g0, a[k][0]); mma8(g1, a[k][1]); mma8(g0 + 4, a[k][2]); mma8(g1 + 4, a[k][3]);
        }
#pragma unroll
        for (int i = 0; i < 4; i++) { g0[i] += g0[i + 4]; g1[i] += g1[i + 4]; }
        const int src = (lane & ~3) | (r >> 1);
        const float q0 = __shfl_sync(~0u, (r & 1) ? g0[1] : g0[0], src), q1 = __shfl_sync(~0u, (r & 1) ? g1[1] : g1[0], src);
        const float sm[3] = {__shfl_sync(~0u, (r & 1) ? g0[3] : g0[2], src), 0.f, __shfl_sync(~0u, (r & 1) ? g1[3] : g1[2], src)};
        if (lane == 0) mbar_arrive(BAR(B_XFREE));
        STAMP(2);
        const float mu0 = sm[0] * (1.f / 512), mu1 = sm[2] * (1.f / 512);
        const float rs0 = rsqrtf(fmaxf(q0 * (1.f / 512) - mu0 * mu0, 0.f) + 1e-5f), rs1 = rsqrtf(fmaxf(q1 * (1.f / 512) - mu1 * mu1, 0.f) + 1e-5f);
        u0 = dup(rs0); u1 = dup(rs1); l0 = dup(rs0 - blo(u0)); l1 = dup(rs1 - blo(u1)); n0 = dup(-mu0 * rs0); n1 = dup(-mu1 * rs1);
        for (uint32_t it = 0; it < SPIN_MAX; it++) {
          uint32_t bad = 0;
#pragma unroll
          for (int i = 0; i < 16; i++) bad |= v[i / 4][i % 4] ^ ep;
          if (!__any_sync(~0u, bad & 0xff)) break;
          ld_grp<4>(v, msrc);
        }
        auto tot = [&](int j) { return __float_as_uint(bfr((__uint_as_float(v[0][j] & ~0xffu) + __uint_as_float(v[1][j] & ~0xffu)) + (__uint_as_float(v[2][j] & ~0xffu) + __uint_as_float(v[3][j] & ~0xffu)))); };
        put_tab(sb + TAB_OFF, (tid & 127) * 4, tid >> 7, make_uint4(tot(0), tot(1), tot(2), tot(3)));
        bar_cons();
        if (bid == 0 && tid == 0) *(volatile uint32_t*)&g_epoch = ep;
      }
      STAMP(3);
      {
        float accA[32], accB[32];
        uint32_t hb[8][4];
        auto tile = [&](float (&acc)[32], int c, int pos, int par) {
          mbar_wait(BAR(B_FULL + pos), par);
          const uint64_t db = mkdesc(sb + pos * CH, 8192, 1024, 1);
          wg_fence();
#pragma unroll
          for (int kk = 0; kk < 8; kk++) wgmma_rs_n64(acc, a[8 * c + kk], db + kk * 128, c | kk);
          wg_commit();
        };
        const uint4 *h1 = &g_kv[m ? bid - 8 : bid][0][tid], *h0 = m > 1 ? h1 - 8 * 2048 : h1;
        auto halo = [&](uint32_t (*hb)[4], int v) {
          fix_grp<8>(hb, [&](int i) { return (i < 4 ? h0 : h1) + (v * 4 + (i & 3)) * 256; }, tg, 26);
#pragma unroll
          for (int i = 0; i < 8; i++) stsm4(srow + (4 + 3 * v + (i >> 2)) * CH + (ssw ^ ((i & 3) * 32)), hb[i][0], hb[i][1], hb[i][2], hb[i][3]);
        };
        auto publish = [&](float (&acc)[32], int v) {
          keep(acc);
          uint32_t p[16];
#pragma unroll
          for (int i = 0; i < 16; i++) p[i] = pack(acc[2 * i], acc[2 * i + 1]);
          if (v) ld_grp<8>(hb, [&](int i) { return (i < 4 ? h0 : h1) + (i & 3) * 256; });
#pragma unroll
          for (int i = 0; i < 4; i++) {
            if (m < 15) st_ll(&g_kv[bid][v * 4 + i][tid], p[4 * i], p[4 * i + 1], p[4 * i + 2], p[4 * i + 3], tg);
            stsm4(srow + (6 + 3 * v) * CH + (ssw ^ (i * 32)), p[4 * i], p[4 * i + 1], p[4 * i + 2], p[4 * i + 3]);
          }
        };
#pragma unroll
        for (int k = 0; k < 32; k += KB) {
#pragma unroll
          for (int j = k ? k + KL : 0; j < k + KB + KL && j < 32; j++) {
            const uint4 t = lds4(tabq + j * 64);
            a[j][0] = hfma2(a[j][0], u0, hfma2(a[j][0], l0, n0)); a[j][1] = hfma2(a[j][1], u1, hfma2(a[j][1], l1, n1));
            a[j][2] = hfma2(a[j][2], u0, hfma2(a[j][2], l0, n0)); a[j][3] = hfma2(a[j][3], u1, hfma2(a[j][3], l1, n1));
            a[j][0] = hfma2(a[j][0], t.x, t.z); a[j][1] = hfma2(a[j][1], t.x, t.z); a[j][2] = hfma2(a[j][2], t.y, t.w); a[j][3] = hfma2(a[j][3], t.y, t.w);
          }
          if (k % 8 == 0) mbar_wait(BAR(B_FULL + k / 8), 0);
          const uint64_t db = mkdesc(sb + k / 8 * CH, 8192, 1024, 1) + k % 8 * 128;
          wg_fence();
#pragma unroll
          for (int i = 0; i < KB; i++) wgmma_rs_n64(accA, a[k + i], db + i * 128, k | i);
          wg_commit();
          if (k && k % 8 == 0) { wg_wait<1>(); release(k / 8 - 1); }
        }
        warp_arrive(BAR(B_TABFREE));
        tile(accB, 0, 10, 0);
        wg_wait<1>();
        release(3);
        publish(accA, 0);
        STAMP(4);
#pragma unroll
        for (int c = 1; c < 4; c++) tile(accB, c, 10 + c, 0);
        tile(accA, 0, 0, 1);
        wg_wait<1>();
        publish(accB, 1);
        tile(accA, 1, 1, 1);
        halo(hb, 0);
        tile(accA, 2, 2, 1);
        ld_grp<8>(hb, [&](int i) { return (i < 4 ? h0 : h1) + (4 + (i & 3)) * 256; });
        tile(accA, 3, 3, 1);
        halo(hb, 1);
        if (lane == 0) { for (int i = 10; i < 14; i++) mbar_arrive(BAR(B_EMPTY + i)); }
        wg_wait<0>();
        keep(accA);
        if (lane == 0) { for (int i = 0; i < 4; i++) mbar_arrive(BAR(B_EMPTY + i)); }
        const float SC = 0.25f * 1.4426950408889634f;
#pragma unroll
        for (int i = 0; i < 16; i++) qf[i] = pack(accA[2 * i] * SC, accA[2 * i + 1] * SC);
        bar_cons();
      }
    }
    STAMP(5);
    const int rb = bid & ~7;
    uint32_t of[4][7][4];
    auto osrc = [&](int h) { return [&, h](int i) { return &g_o[rb + ((g + 1 + i) & 7)][h][tid]; }; };
    {
      const float NINF = __int_as_float(0xff800000);
      const int kbmin = 16 - 8 * m - warp;
      const uint32_t kaddr = sb + 4 * CH + (warp * 16 + (lane & 7) + (lane >> 4) * 8) * 128, ksw = (((lane >> 3) & 1) ^ (lane & 7)) << 4;
      const uint32_t vaddr = srow + 7 * CH;
      const bool p0 = 2 * q <= r, p1 = 2 * q + 1 <= r;
      const uint32_t mk = (p0 ? 0xffffu : 0u) | (p1 ? 0xffff0000u : 0u);
      float o[8], l[4];
      auto qk = [&](float* s, const uint32_t* qq, int h, int j, float b0, float b1) {
        uint32_t kf[4];
        ldsm4(kf, kaddr + j * 2048 + (ksw ^ (h * 32)));
        mma(s, qq[0], qq[1], qq[2], qq[3], kf[0], kf[1], b0, b0, b1, b1);
        mma(s + 4, qq[0], qq[1], qq[2], qq[3], kf[2], kf[3], b0, b0, b1, b1);
      };
      auto pv = [&](uint32_t a0, uint32_t a1, uint32_t a2, uint32_t a3, int h, int j) {
        uint32_t vf[4];
        ldsm4t(vf, vaddr + (ssw ^ (h * 32)) + j * 2048);
        mma_acc(o, a0, a1, a2, a3, vf[0], vf[1]);
        mma_acc(o + 4, a0, a1, a2, a3, vf[2], vf[3]);
      };
      auto bmax = [&](const float* s, float& a0, float& a1) { a0 = fmaxf(fmaxf(a0, fmaxf(s[0], s[1])), fmaxf(s[4], s[5])); a1 = fmaxf(fmaxf(a1, fmaxf(s[2], s[3])), fmaxf(s[6], s[7])); };
      auto qmax = [&](float& a0, float& a1) {
        a0 = fmaxf(a0, __shfl_xor_sync(~0u, a0, 1)); a1 = fmaxf(a1, __shfl_xor_sync(~0u, a1, 1));
        a0 = fmaxf(a0, __shfl_xor_sync(~0u, a0, 2)); a1 = fmaxf(a1, __shfl_xor_sync(~0u, a1, 2));
      };
      auto merged = [&](float* s, const uint32_t* qq, int h, float& r0, float& r1) {
        float f[8];
        const float b = kbmin <= 0 ? 0.f : NINF;
        qk(s, qq, h, 16, 0.f, 0.f); qk(f, qq, h, 0, b, b);
        s[0] = p0 ? s[0] : f[0]; s[1] = p1 ? s[1] : f[1]; s[4] = f[4]; s[5] = f[5]; s[6] = p0 ? s[6] : f[6]; s[7] = p1 ? s[7] : f[7];
        r0 = r1 = NINF;
        bmax(s, r0, r1);
      };
      auto block = [&](const float* s, int h, int j) {
        const uint32_t a0 = pack(ex2(s[0]), ex2(s[1])), a1 = pack(ex2(s[2]), ex2(s[3])), a2 = pack(ex2(s[4]), ex2(s[5])), a3 = pack(ex2(s[6]), ex2(s[7]));
        mma_acc(l, a0, a1, a2, a3, 0x3f803f80u, 0x3f803f80u);
        if (j == 16) { pv(a0 & mk, a1, 0u, a3 & mk, h, 16); pv(a0 & ~mk, 0u, a2, a3 & ~mk, h, 0); }
        else pv(a0, a1, a2, a3, h, j);
      };
      auto first = [&](const float* s, int h, float n0, float n1) {
        const float t[8] = {s[0] + n0, s[1] + n0, s[2] + n1, s[3] + n1, s[4] + n0, s[5] + n0, s[6] + n1, s[7] + n1};
#pragma unroll
        for (int i = 0; i < 8; i++) o[i] = 0.f;
        l[0] = l[1] = l[2] = l[3] = 0.f;
        block(t, h, 16);
      };
      float s0[8], r0, r1;
      merged(s0, qf, 0, r0, r1);
      qmax(r0, r1);
      const bool late = warp >= 4 && RS1;
      auto resets = [&](int h) {
        if (h == 0) { reset(&g_o[bid][3][tid], 1); reset(&g_x1[bid][0][tid], 4); if (q == 0) reset(&g_stats[bid][warp * 8 + r], 1); }
        if (h == 1) reset(&g_p[bid][0][tid], 4);
        if (h == 2) reset(&g_h[bid][0][tid], RH);
      };
      auto side = [&](int h) {
            {
              if (h == 0) { if (!late) resets(0); }
              else if (h == 1) { ld_grp<7>(of[0], osrc(0)); if (!late) resets(1); }
              else if (h == 2) { ld_grp<7>(of[1], osrc(1)); if (!late) resets(2); }
              else ld_grp<7>(of[2], osrc(2));
            }
      };
      auto run = [&](auto full) {
#pragma unroll 1
        for (int h = 0; h < 4; h++) {
          const float n0 = -r0, n1 = -r1;
          first(s0, h, n0, n1);
#pragma unroll
          for (int j = 15; j >= 1; j--) {
            float s[8];
            const bool ok = decltype(full)::value || j >= kbmin;
            qk(s, qf, h, j, ok ? n0 : NINF, ok ? n1 : NINF);
            block(s, h, j);
            if (j == LDJ) side(h);
            if (j == 8) { merged(s0, qf + 4, (h + 1) & 3, r0, r1); qmax(r0, r1); }
          }
          if (__any_sync(~0u, !(l[0] < 1e18f) || !(l[2] < 1e18f))) {
            float t[8], s[8], m0, m1;
            const int jlo = kbmin > 1 ? kbmin : 1;
            merged(t, qf, h, m0, m1);
#pragma unroll 1
            for (int j = 15; j >= jlo; j--) { qk(s, qf, h, j, 0.f, 0.f); bmax(s, m0, m1); }
            qmax(m0, m1);
            first(t, h, -m0, -m1);
#pragma unroll 1
            for (int j = 15; j >= jlo; j--) { qk(s, qf, h, j, -m0, -m1); block(s, h, j & 15); }
          }
          const float i0 = __fdividef(1.f, l[0]), i1 = __fdividef(1.f, l[2]);
#pragma unroll
          for (int i = 0; i < 12; i++) qf[i] = qf[i + 4];
          qf[12] = pack(o[0] * i0, o[1] * i0); qf[13] = pack(o[2] * i1, o[3] * i1); qf[14] = pack(o[4] * i0, o[5] * i0); qf[15] = pack(o[6] * i1, o[7] * i1);
          st_ll(&g_o[bid][h][tid], qf[12], qf[13], qf[14], qf[15], tg);
          if (LDJ == 0) side(h);
        }
      };
      if (warp >= 4) { long long tt = clock64(); if (RS1) { resets(0); resets(1); resets(2); } while (clock64() - tt < STG); }
      if (m >= 2) run(std::true_type{}); else run(std::false_type{});
    }
    STAMP(6);
    uint32_t xr[4][4], h0, h1, l0, l1, n0, n1;
    uint32_t xb[2][4][4];
    {
      const uint32_t* xp = (const uint32_t*)(P.x + (size_t)(m * 128 + warp * 16 + r) * 512 + colblk(g) * 64) + q;
#pragma unroll
      for (int j = 0; j < 8; j++) { xr[j / 2][(j & 1) * 2] = __ldg(xp + j * 4); xr[j / 2][(j & 1) * 2 + 1] = __ldg(xp + 8 * 256 + j * 4); }
      float acc[32];
      if (OLDE) warp_arrive(BAR(B_OLD));
#pragma unroll
      for (int h = 0; h < 4; h++) {
        uint32_t own[4] = {qf[4 * h], qf[4 * h + 1], qf[4 * h + 2], qf[4 * h + 3]};
        fix_grp<7>(of[h], osrc(h), tg, 27);
        mbar_wait(BAR(B_FULL + 10 + h), 1);
        const uint64_t db = mkdesc(sb + (10 + h) * CH, 8192, 1024, 1);
        wg_fence();
#pragma unroll
        for (int s = 0; s < 8; s++) wgmma_rs_n64(acc, s ? of[h][s - 1] : own, db + ((g + s) & 7) * 128, h | s);
        wg_commit();
        if (h == WOJ) ld_grp<7>(of[3], osrc(3));
      }
      mbar_wait(BAR(B_MOD2), 0);
      wg_wait<0>();
      keep(acc);
      STAMP(7);
      if (lane == 0) { for (int i = 10; i < 14; i++) mbar_arrive(BAR(B_EMPTY + i)); }
      float s0 = 0, s1 = 0, q0 = 0, q1 = 0;
#pragma unroll
      for (int j = 0; j < 8; j++) {
        const uint32_t ga = lds1(sb + GAB_OFF + j * 16 + q * 4);
        uint32_t& u = xr[j / 2][(j & 1) * 2]; uint32_t& w = xr[j / 2][(j & 1) * 2 + 1];
        u = pack(fmaf(blo(ga), acc[4 * j], blo(u)), fmaf(bhi(ga), acc[4 * j + 1], bhi(u)));
        w = pack(fmaf(blo(ga), acc[4 * j + 2], blo(w)), fmaf(bhi(ga), acc[4 * j + 3], bhi(w)));
        const float a = blo(u), b = bhi(u), c = blo(w), d = bhi(w);
        s0 += a + b; q0 = fmaf(a, a, fmaf(b, b, q0)); s1 += c + d; q1 = fmaf(c, c, fmaf(d, d, q1));
      }
#pragma unroll
      for (int o = 1; o < 4; o <<= 1) { s0 += __shfl_xor_sync(~0u, s0, o); s1 += __shfl_xor_sync(~0u, s1, o); q0 += __shfl_xor_sync(~0u, q0, o); q1 += __shfl_xor_sync(~0u, q1, o); }
      if (q == 0) st_ll(&g_stats[bid][warp * 8 + r], __float_as_uint(s0), __float_as_uint(q0), __float_as_uint(s1), __float_as_uint(q1), tg);
#pragma unroll
      for (int h = 0; h < SX; h++) st_ll(&g_x1[bid][h][tid], xr[h][0], xr[h][1], xr[h][2], xr[h][3], tg);
      uint32_t vw[2][4];
      uint32_t(&v)[4] = vw[0], (&w)[4] = vw[1];
      const uint4* sp = &g_stats[rb + q * 2][warp * 8 + r];
      ld_ll(v, sp); ld_ll(w, sp + 64);
#pragma unroll
      for (int h = SX; h < 4; h++) st_ll(&g_x1[bid][h][tid], xr[h][0], xr[h][1], xr[h][2], xr[h][3], tg);
      fix_grp<2>(vw, [&](int i) { return sp + i * 64; }, tg, 28);
      if (!OLDE && lane == 0) mbar_arrive(BAR(B_OLD));
      ld_grp<4>(xb[1], [&](int h) { return &g_x1[rb + ((g + 1) & 7)][h][tid]; });
#pragma unroll
      for (int i = 0; i < 16; i++) xb[0][i / 4][i % 4] = i % 4 ? xr[i / 4][i % 4] : (xr[i / 4][0] & ~1u) | tg;
      s0 = __uint_as_float(v[0]) + __uint_as_float(w[0]); q0 = __uint_as_float(v[1]) + __uint_as_float(w[1]);
      s1 = __uint_as_float(v[2]) + __uint_as_float(w[2]); q1 = __uint_as_float(v[3]) + __uint_as_float(w[3]);
#pragma unroll
      for (int o = 1; o < 4; o <<= 1) { s0 += __shfl_xor_sync(~0u, s0, o); s1 += __shfl_xor_sync(~0u, s1, o); q0 += __shfl_xor_sync(~0u, q0, o); q1 += __shfl_xor_sync(~0u, q1, o); }
      const float mu0 = s0 * (1.f / 512), mu1 = s1 * (1.f / 512);
      const float rs0 = rsqrtf(fmaxf(q0 * (1.f / 512) - mu0 * mu0, 0.f) + 1e-5f), rs1 = rsqrtf(fmaxf(q1 * (1.f / 512) - mu1 * mu1, 0.f) + 1e-5f);
      h0 = dup(rs0); h1 = dup(rs1); l0 = dup(rs0 - blo(h0)); l1 = dup(rs1 - blo(h1)); n0 = dup(-mu0 * rs0); n1 = dup(-mu1 * rs1);
    }
    STAMP(8);
    uint32_t hf[14][4];
    {
      float acc[112];
      uint32_t a[2][4][4];
#pragma unroll
      for (int i = 0; i < 112; i++) acc[i] = 0.f;
#pragma unroll UN1
      for (int c2 = 0; c2 < 8; c2 += 2) {
#pragma unroll
        for (int e = 0; e < 2; e++) {
          const int c = c2 + e;
          const uint32_t tb = tabq + colblk((g + c) & 7) * 256;
          fix_grp<4>(xb[e], [&](int h) { return &g_x1[rb + ((g + c) & 7)][h][tid]; }, tg, 29);
#pragma unroll
          for (int h = 0; h < 4; h++) {
            const uint4 t = lds4(tb + h * 64);
            const uint32_t* x = xb[e][h];
            a[e][h][0] = hfma2(hfma2(x[0], h0, hfma2(x[0], l0, n0)), t.x, t.z); a[e][h][1] = hfma2(hfma2(x[1], h1, hfma2(x[1], l1, n1)), t.x, t.z);
            a[e][h][2] = hfma2(hfma2(x[2], h0, hfma2(x[2], l0, n0)), t.y, t.w); a[e][h][3] = hfma2(hfma2(x[3], h1, hfma2(x[3], l1, n1)), t.y, t.w);
          }
          if (c2 < 6) ld_grp<4>(xb[e], [&](int h) { return &g_x1[rb + ((g + c + 2) & 7)][h][tid]; });
          const int pos = c == 7 ? 0 : 2 * c, prev = 2 * c - 2;
          mbar_wait(BAR(B_FULL + pos), c == 7); mbar_wait(BAR(B_FULL + pos + 1), c == 7);
          const uint64_t db = mkdesc(sb + pos * CH, 2048, 512, 2);
          wg_fence();
#pragma unroll
          for (int h = 0; h < 4; h++) wgmma_rs_n224(acc, a[e][h], db + (h >> 1) * (CH / 16) + (h & 1) * 64, 1);
          wg_commit();
          wg_wait<1>();
          if (c && lane == 0) { mbar_arrive(BAR(B_EMPTY + prev)); mbar_arrive(BAR(B_EMPTY + prev + 1)); }
        }
      }
      wg_wait<0>();
      keep(acc);
      if (lane == 0) { mbar_arrive(BAR(B_EMPTY + 0)); mbar_arrive(BAR(B_EMPTY + 1)); }
#pragma unroll
      for (int u = 0; u < 14; u++) {
        const int k = (u + 8) % 14;
#pragma unroll
        for (int i = 0; i < 4; i++) hf[k][i] = pack_relu(acc[8 * k + 2 * i], acc[8 * k + 2 * i + 1]);
        hf[k][0] = (hf[k][0] & ~1u) | tg;
        if (u < 4) st_ll(&g_h[bid][u][tid], hf[k][0], hf[k][1], hf[k][2], hf[k][3], tg);
      }
    }
    STAMP(9);
    {
      float acc[64];
      uint32_t pb[4][4][4];
      const uint4* hp[3];
#pragma unroll
      for (int i = 0; i < 3; i++) hp[i] = &g_h[rb + ((g & 4) | ((g + 1 + i) & 3))][0][tid];
      auto hsrc = [&](int ks) { const int v = (ks >> 1) - 7 + 3; return hp[v % 3] + ((v / 3 - 1) * 2 + (ks & 1)) * 256; };
      auto pub = [&](int u0, int u1) {
#pragma unroll
        for (int u = u0; u < u1; u++) { const uint32_t* f = hf[(u + 8) % 14]; st_ll(&g_h[bid][u][tid], f[0], f[1], f[2], f[3], tg); }
      };
      auto mm = [&](uint32_t (*a)[4], int pos, int par, int G) {
        mbar_wait(BAR(B_FULL + pos), par);
        const uint64_t db = mkdesc(sb + pos * CH, 4096, 1024, 1);
        wg_fence();
#pragma unroll
        for (int i = 0; i < 4; i++) wgmma_rs_n128(acc, a[i], db + (i >> 1) * 512 + (i & 1) * 128, G | i);
        wg_commit();
      };
#pragma unroll
      for (int G = 0; G < 2; G++) {
        mm(hf + 4 * G, 2 + G, 1, G);
        if (G) pub(4, 6);
      }
#pragma unroll
      for (int i = 0; i < 24; i++) pb[i / 16][(i / 4) & 3][i & 3] = hf[8 + i / 4][i & 3];
      wg_wait<1>();
      release(2);
      STAMP(10);
      uint64_t posq = 0x10dcba987654ull;
#pragma unroll UN2
      for (int it = 0; it < 3; it++) {
#pragma unroll
        for (int e = 0; e < 4; e++) {
          if (e == 1 && it == 0) fix_grp<2>(pb[1] + 2, [&](int i) { return hsrc(14 + i); }, tg, 30);
          else if (e || it) fix_grp<4>(pb[e], [&](int i) { return hsrc(8 + 4 * e + i); }, tg, 30);
          mm(pb[e], posq & 15, (posq & 14) != 0, 1);
          posq >>= 4;
          if (e == 0 && it == 1) STAMP(20);
          if (e == 1 && it == 0) STAMP(18);
          if (e == 2 && it == 0) STAMP(19);
          if (e == 0 && it == 0) STAMP(21);
          wg_wait<1>();
          if (e == 0 && it == 0) {
            ld_grp<2>(pb[1] + 2, [&](int i) { return hsrc(14 + i); });
            ld_grp<4>(pb[2], [&](int i) { return hsrc(16 + i); });
            if (EARLY) wg_wait<0>();
          }
          if (e == 1 - EARLY && it == 0) ld_grp<4>(pb[3], [&](int i) { return hsrc(20 + i); });
          if (e == 0 ? it > 0 : it < 2) ld_grp<4>(pb[(e + 3) & 3], [&](int i) { return hsrc(20 + 4 * e + i); });
          if (PACE == 0) { if (it == 0) pub(6 + 2 * e, 8 + 2 * e); }
          else if (it == 0) pub(e < 2 ? 6 + e : 7 + e, e < 1 ? 7 : 8 + e);
          else if (it == 1 && e < 2) pub(11 + 2 * e, 13 + e);
        }
        if (it == 2) {
#pragma unroll
          for (int h = 0; h < 4; h++) { uint32_t t[4]; ld_ll(t, &g_x1[bid][h][tid]); xr[h][1] = t[1]; xr[h][2] = t[2]; xr[h][3] = t[3]; }
        }
        const uint4* t = hp[2] + 1024; hp[2] = hp[1] + 1536; hp[1] = hp[0] + 1536; hp[0] = t;
      }
      wg_wait<0>();
      keep(acc);
      STAMP(11);
      const bool kh = g >> 2;
      uint32_t pp[4][4];
#pragma unroll
      for (int i = 0; i < 16; i++) pp[i / 4][i % 4] = pack(kh ? acc[2 * i] : acc[32 + 2 * i], kh ? acc[2 * i + 1] : acc[33 + 2 * i]);
#pragma unroll
      for (int h = 0; h < 4; h++) st_ll(&g_p[bid][h][tid], pp[h][0], pp[h][1], pp[h][2], pp[h][3], tg);
#pragma unroll
      for (int i = 0; i < 32; i++) acc[i] = kh ? acc[32 + i] : acc[i];
      mbar_wait(BAR(B_EMPTY + 2), 1);
      STAMP(12);
      auto psrc = [&](int h) { return &g_p[bid ^ 4][h][tid]; };
      ld_grp<4>(pp, psrc);
      fix_grp<4>(pp, psrc, tg, 25);
      STAMP(13);
#pragma unroll
      for (int h = 0; h < 4; h++) {
        const uint32_t g0 = lds1(sb + GAB_OFF + 128 + h * 32 + q * 4), g1 = lds1(sb + GAB_OFF + 128 + h * 32 + 16 + q * 4);
        const float* f = acc + 8 * h; const uint32_t* x = xr[h]; const uint32_t* y = pp[h];
        stsm4(srow + 2 * CH + (ssw ^ (h * 32)),
              pack(fmaf(blo(g0), f[0] + blo(y[0]), blo(x[0])), fmaf(bhi(g0), f[1] + bhi(y[0]), bhi(x[0]))), pack(fmaf(blo(g0), f[2] + blo(y[1]), blo(x[1])), fmaf(bhi(g0), f[3] + bhi(y[1]), bhi(x[1]))),
              pack(fmaf(blo(g1), f[4] + blo(y[2]), blo(x[2])), fmaf(bhi(g1), f[5] + bhi(y[2]), bhi(x[2]))), pack(fmaf(blo(g1), f[6] + blo(y[3]), blo(x[3])), fmaf(bhi(g1), f[7] + bhi(y[3]), bhi(x[3]))));
      }
      fence_async();
      __syncwarp();
      if (lane == 0) {
        asm volatile("cp.async.bulk.tensor.2d.global.shared::cta.bulk_group [%0, {%2, %3}], [%1];" ::"l"(&tm_out), "r"(sb + 2 * CH + warp * 2048), "r"(colblk(g) * 64), "r"(m * 128 + warp * 16) : "memory");
        asm volatile("cp.async.bulk.commit_group;\ncp.async.bulk.wait_group.read 0;" ::: "memory");
      }
      STAMP(14);
    }
  }
}

typedef CUresult (*EncFn)(CUtensorMap*, CUtensorMapDataType, cuuint32_t, void*, const cuuint64_t*, const cuuint64_t*, const cuuint32_t*, const cuuint32_t*,
                          CUtensorMapInterleave, CUtensorMapSwizzle, CUtensorMapL2promotion, CUtensorMapFloatOOBfill);

extern "C" void kernel_launch(void* const* d_in, const int* in_sizes, int n_in, void* d_out, int out_size) {
  static EncFn enc = nullptr;
  static void* epoch = nullptr;
  if (!enc) {
    void* fn = nullptr; cudaDriverEntryPointQueryResult qr;
    cudaGetDriverEntryPoint("cuTensorMapEncodeTiled", &fn, cudaEnableDefault, &qr);
    enc = (EncFn)fn;
    cudaGetSymbolAddress(&epoch, g_epoch);
    cudaFuncSetAttribute(fused_kernel, cudaFuncAttributeMaxDynamicSharedMemorySize, SMEM_BYTES);
  }
  auto mk = [&](void* p, int rank, uint64_t d0, uint64_t d1, uint64_t d2, uint64_t s1, uint64_t s2, uint32_t b0, uint32_t b1, uint32_t b2, CUtensorMapSwizzle sw) {
    CUtensorMap tm; cuuint64_t dims[3] = {d0, d1, d2}, str[2] = {s1, s2}; cuuint32_t box[3] = {b0, b1, b2}, es[3] = {1, 1, 1};
    enc(&tm, CU_TENSOR_MAP_DATA_TYPE_BFLOAT16, rank, p, dims, str, box, es, CU_TENSOR_MAP_INTERLEAVE_NONE, sw, CU_TENSOR_MAP_L2_PROMOTION_L2_128B, CU_TENSOR_MAP_FLOAT_OOB_FILL_NONE);
    return tm;
  };
  const CUtensorMap tx = mk(d_in[0], 3, 64, 2048, 8, 1024, 128, 64, 128, 2, CU_TENSOR_MAP_SWIZZLE_128B);
  const CUtensorMap tq = mk(d_in[1], 3, 512, 512, 3, 3072, 1024, 64, 128, 1, CU_TENSOR_MAP_SWIZZLE_128B);
  const CUtensorMap to = mk(d_in[2], 3, 512, 64, 8, 1024, 65536, 64, 16, 8, CU_TENSOR_MAP_SWIZZLE_128B);
  const CUtensorMap t1 = mk(d_in[4], 3, 32, 512, 56, 3584, 64, 32, 32, 7, CU_TENSOR_MAP_SWIZZLE_64B);
  const CUtensorMap t2 = mk(d_in[5], 3, 64, 1792, 8, 1024, 128, 64, 32, 2, CU_TENSOR_MAP_SWIZZLE_128B);
  const CUtensorMap tout = mk(d_out, 2, 512, 2048, 1, 1024, 0, 64, 16, 1, CU_TENSOR_MAP_SWIZZLE_128B);
  Params P{(const __nv_bfloat16*)d_in[0], (const __nv_bfloat16*)d_in[1], (const __nv_bfloat16*)d_in[2], (const __nv_bfloat16*)d_in[4], (const __nv_bfloat16*)d_in[5],
           (const __nv_bfloat16*)d_in[6], (const __nv_bfloat16*)d_in[7], (const uint32_t*)epoch};
  fused_kernel<<<128, 384, SMEM_BYTES>>>(tx, tq, to, t1, t2, tout, P);
}
```
